```python
import torch

def _softmax(x, axis=-1):
    return torch.softmax(x, dim=axis)
def _gelu(x):
    return torch.nn.functional.gelu(x, approximate="tanh")
def _silu(x):
    return torch.nn.functional.silu(x)
def _sigmoid(x):
    return torch.sigmoid(x)
def _layernorm(x, axis=-1, eps=1e-5):
    m = x.mean(dim=axis, keepdim=True)
    v = x.var(dim=axis, keepdim=True, unbiased=False)
    return (x - m) / torch.sqrt(v + eps)
def _scatter_add(tgt, idx, src, axis=0):
    return tgt.clone().index_add_(axis, idx, src)
def _segment_sum(src, seg, n):
    out = torch.zeros((n,) + src.shape[1:], dtype=src.dtype)
    return out.index_add_(0, seg, src)
def _pad(x, pw):
    flat = tuple(v for pair in reversed(pw) for v in pair)
    return torch.nn.functional.pad(x, flat)

kernel_name = 'parallel_sum__ssm_conv_s4__moe_arch_mod__prompt'

def setup_inputs():

    _w = (lambda a: (lambda t: t.to(torch.bfloat16) if t.is_floating_point() else t)(torch.as_tensor(a)))
    def _A_setup():
        B, L, D, N = 1, 2048, 512, 128
        A_re = -(lambda _x: torch.exp(torch.as_tensor(_x)))((lambda *s: torch.randn(*s, dtype=torch.bfloat16) * 3.2)(D, N))
        A_im = torch.pi * (lambda *s: torch.randn(*s, dtype=torch.bfloat16) * 0.1)(D, N)
        B_re = (lambda *s: torch.randn(*s, dtype=torch.bfloat16) * 0.4)(D, N)
        B_im = (lambda *s: torch.randn(*s, dtype=torch.bfloat16) * 0.4)(D, N)
        C_re = (lambda *s: torch.randn(*s, dtype=torch.bfloat16) * 0.4)(D, N)
        C_im = (lambda *s: torch.randn(*s, dtype=torch.bfloat16) * 0.4)(D, N)
        log_dt = (lambda *s: torch.randn(*s, dtype=torch.bfloat16) * 0.1)(D) * 0.5 - 4.0
        Dskip = (lambda *s: torch.randn(*s, dtype=torch.bfloat16) * 0.1)(D)
        return {
            "u": _w((lambda *s: torch.randn(*s, dtype=torch.bfloat16) * 0.05)(B, L, D)),
            "A_re": _w(A_re),
            "A_im": _w(A_im),
            "B_re": _w(B_re),
            "B_im": _w(B_im),
            "C_re": _w(C_re),
            "C_im": _w(C_im),
            "log_dt": _w(log_dt),
            "Dskip": _w(Dskip),
        }
    _A_in = _A_setup()

    def _B_setup():
        B, S, D, F, C = 1, 2048, 512, 1792, 1
        return {
            "x": _w((lambda *s: torch.randn(*s, dtype=torch.bfloat16) * 0.05)(B, S, D)),
            "w_r": _w((lambda *s: torch.randn(*s, dtype=torch.bfloat16) * 0.05)(D)),
            "w_gate": _w((lambda *s: torch.randn(*s, dtype=torch.bfloat16) * 0.05)(D, F)),
            "w_up": _w((lambda *s: torch.randn(*s, dtype=torch.bfloat16) * 0.05)(D, F)),
            "w_down": _w((lambda *s: torch.randn(*s, dtype=torch.bfloat16) * 0.05)(F, D)),
        }
    _B_in = _B_setup()

    return {
        "A_u": _A_in["u"],
        "A_A_re": _A_in["A_re"],
        "A_A_im": _A_in["A_im"],
        "A_B_re": _A_in["B_re"],
        "A_B_im": _A_in["B_im"],
        "A_C_re": _A_in["C_re"],
        "A_C_im": _A_in["C_im"],
        "A_log_dt": _A_in["log_dt"],
        "A_Dskip": _A_in["Dskip"],
        "B_x": _B_in["x"],
        "B_w_r": _B_in["w_r"],
        "B_w_gate": _B_in["w_gate"],
        "B_w_up": _B_in["w_up"],
        "B_w_down": _B_in["w_down"],
    }

def reference(A_u, A_A_re, A_A_im, A_B_re, A_B_im, A_C_re, A_C_im, A_log_dt, A_Dskip, B_x, B_w_r, B_w_gate, B_w_up, B_w_down):
    def _A_ref(u, A_re, A_im, B_re, B_im, C_re, C_im, log_dt, Dskip):
        Bsz, L, D = u.shape
        dt = torch.exp(log_dt)[:, None]
        A = A_re + 1j * A_im
        Bc = B_re + 1j * B_im
        Cc = C_re + 1j * C_im
        logdA = dt * A
        dB = dt * Bc
        l = (lambda x, dt: x.to(dt))(torch.arange(L), A_re.dtype)
        P = torch.exp(logdA[:, :, None] * l[None, None, :])
        K = torch.einsum("dn,dnl,dn->dl", Cc, P, dB).real
        L2 = 2 * L
        Kp = _pad(K, ((0, 0), (0, L)))
        up = (lambda x, *d: x.permute(*d))(u, 0, 2, 1)
        up = _pad(up, ((0, 0), (0, 0), (0, L)))
        Kf = (lambda x, axes=(-2,-1): torch.fft.rfft2(x.float(), dim=axes))(Kp[:, None, :], axes=(-2, -1))
        Uf = (lambda x, axes=(-2,-1): torch.fft.rfft2(x.float(), dim=axes))(up[:, :, None, :], axes=(-2, -1))
        Yf = Uf * Kf[None, :, :, :]
        y = (lambda x, s, axes=(-2,-1): torch.fft.irfft2(x, s=s, dim=axes).to(torch.bfloat16))(Yf, (1, L2), axes=(-2, -1))[:, :, 0, :L]
        y = (lambda x, *d: x.permute(*d))(y, 0, 2, 1) + u * Dskip[None, None, :]
        return y

    def _B_ref(x, w_r, w_gate, w_up, w_down):
        B, S, D = x.shape
        C = 1
        r = x @ w_r
        idx = torch.argsort(-r, axis=-1)[:, :C]
        idx_e = (lambda x, n, axis: torch.repeat_interleave(x, n, dim=axis))(idx.reshape(B, C, 1), D, axis=2)
        x_sel = (lambda x, i, axis: torch.take_along_dim(x, i, dim=axis))(x, idx_e, axis=1)
        g = _silu(x_sel @ w_gate)
        u = x_sel @ w_up
        y = (g * u) @ w_down
        r_sel = _sigmoid((lambda x, i, axis: torch.take_along_dim(x, i, dim=axis))(r, idx, axis=1))
        y = y * r_sel.reshape(B, C, 1)
        b_off = (torch.arange(B) * S).reshape(B, 1)
        flat_idx = (idx + b_off).reshape(B * C)
        zero = (x * 0.0).reshape(B * S, D)
        upd = _scatter_add(zero, flat_idx, y.reshape(B * C, D), axis=0)
        return x + upd.reshape(B, S, D)

    x = A_u
    xn = _layernorm(x, axis=-1)
    return x + _A_ref(xn, A_A_re, A_A_im, A_B_re, A_B_im, A_C_re, A_C_im, A_log_dt, A_Dskip) + _B_ref(xn, B_w_r, B_w_gate, B_w_up, B_w_down)
```

```cpp
#include <cuda_runtime.h>
#include <cuda.h>
#include <cuda_bf16.h>
#include <cuda_fp16.h>
#include <stdint.h>

#define NCTA 128
#define NTHR 512
#define SPIN_MAX (1 << 20)
#define XDELAY 400

constexpr int G_EPOCH = 0;
constexpr int G_CNT1 = 128;
constexpr int G_CNT2 = 256;
constexpr int G_RINFO = 1024;
constexpr int G_H = 2048;
constexpr int G_PART = 10240;
constexpr int G_S1 = 32768;
__device__ __align__(1024) uint8_t g_scr[G_S1 + 2097152];

#define STAMPT(i, t)
#define STAMPW(i)

constexpr int US = 5376;
constexpr int SM_U = 0;
constexpr int SM_TAP = 21504;
constexpr int TAPS = 3968;
constexpr int T_L0 = 0, T_L1 = 1152, T_L2 = 2432, T_L3 = 3200;
constexpr int SM_S = 37376;
constexpr int SM_MISC = 53760;
constexpr int SM_WG = 55296;
constexpr int SM_WU = SM_WG + 16384;
constexpr int SM_WD = SM_WU + 16384;
constexpr int SM_ARR = SM_WD + 14336;
constexpr int AS = 30080;
constexpr int A_A0 = 0;
constexpr int A_B0 = 3840, A_A1 = 7424, A_B1 = 11008;
constexpr int A_W5 = 14592;
constexpr int A_W9 = 17920, A_W7 = 20480;
constexpr int A_P2 = 23040;
constexpr int A_Y0 = 25344;
constexpr int SM_GRED = SM_ARR + 4 * AS;
constexpr int SM_STAMP = SM_GRED + 2560;
constexpr int SMEM_BYTES = SM_GRED + 2560;
static_assert(SMEM_BYTES <= 232448, "smem");
constexpr int SM_KG = SM_ARR;
constexpr int SM_XT = SM_ARR + 65536;
constexpr int SM_LT = SM_XT + 16640;
constexpr int SM_P1 = SM_LT + 16384;
constexpr int SM_WR = SM_P1 + 4096;
constexpr int MB_W1 = SM_MISC, MB_W2 = SM_MISC + 8, MB_X2 = SM_MISC + 16, MB_G = SM_MISC + 24;
constexpr int MB_TILE = SM_MISC + 32;
constexpr int MB_Y0 = SM_MISC + 96;
constexpr int MB_Y1 = SM_MISC + 128;
constexpr int MB_Y3 = SM_MISC + 160;
constexpr int MB_VS = SM_MISC + 168;
constexpr int M_STAT = SM_MISC + 400;
constexpr int M_CH = SM_MISC + 528;
constexpr int M_IDX = SM_MISC + 592;
constexpr int M_VS = SM_MISC + 608;
constexpr int M_PRE = SM_MISC + 624;
constexpr int M_RED = SM_MISC + 656;
constexpr int M_XS = SM_GRED + 2048;

__device__ __forceinline__ uint32_t lds32(uint32_t a) { uint32_t v; asm volatile("ld.shared.u32 %0, [%1];" : "=r"(v) : "r"(a)); return v; }
__device__ __forceinline__ float ldsf(uint32_t a) { float v; asm volatile("ld.shared.f32 %0, [%1];" : "=f"(v) : "r"(a)); return v; }
__device__ __forceinline__ uint4 lds128(uint32_t a) { uint4 v; asm volatile("ld.shared.v4.u32 {%0,%1,%2,%3}, [%4];" : "=r"(v.x), "=r"(v.y), "=r"(v.z), "=r"(v.w) : "r"(a)); return v; }
__device__ __forceinline__ uint2 lds64(uint32_t a) { uint2 v; asm volatile("ld.shared.v2.u32 {%0,%1}, [%2];" : "=r"(v.x), "=r"(v.y) : "r"(a)); return v; }
__device__ __forceinline__ void sts64(uint32_t a, uint32_t x, uint32_t y) { asm volatile("st.shared.v2.u32 [%0], {%1,%2};" :: "r"(a), "r"(x), "r"(y) : "memory"); }
__device__ __forceinline__ void sts16(uint32_t a, uint16_t v) { asm volatile("st.shared.u16 [%0], %1;" :: "r"(a), "h"(v) : "memory"); }
__device__ __forceinline__ void sts32(uint32_t a, uint32_t v) { asm volatile("st.shared.u32 [%0], %1;" :: "r"(a), "r"(v) : "memory"); }
__device__ __forceinline__ void stsf(uint32_t a, float v) { asm volatile("st.shared.f32 [%0], %1;" :: "r"(a), "f"(v) : "memory"); }
__device__ __forceinline__ void sts64f(uint32_t a, float x, float y) { asm volatile("st.shared.v2.f32 [%0], {%1,%2};" :: "r"(a), "f"(x), "f"(y) : "memory"); }
__device__ __forceinline__ void sts128(uint32_t a, uint32_t x, uint32_t y, uint32_t z, uint32_t w) { asm volatile("st.shared.v4.u32 [%0], {%1,%2,%3,%4};" :: "r"(a), "r"(x), "r"(y), "r"(z), "r"(w) : "memory"); }
__device__ __forceinline__ void ldsm4(uint32_t (&r)[4], uint32_t a) { asm volatile("ldmatrix.sync.aligned.m8n8.x4.shared.b16 {%0,%1,%2,%3}, [%4];" : "=r"(r[0]), "=r"(r[1]), "=r"(r[2]), "=r"(r[3]) : "r"(a) : "memory"); }
__device__ __forceinline__ void ldsm4t(uint32_t (&r)[4], uint32_t a) { asm volatile("ldmatrix.sync.aligned.m8n8.x4.trans.shared.b16 {%0,%1,%2,%3}, [%4];" : "=r"(r[0]), "=r"(r[1]), "=r"(r[2]), "=r"(r[3]) : "r"(a) : "memory"); }
__device__ __forceinline__ void ldsm2t(uint32_t& r0, uint32_t& r1, uint32_t a) { asm volatile("ldmatrix.sync.aligned.m8n8.x2.trans.shared.b16 {%0,%1}, [%2];" : "=r"(r0), "=r"(r1) : "r"(a) : "memory"); }
__device__ __forceinline__ void stsm4(uint32_t a, uint32_t r0, uint32_t r1, uint32_t r2, uint32_t r3) { asm volatile("stmatrix.sync.aligned.m8n8.x4.shared.b16 [%0], {%1,%2,%3,%4};" :: "r"(a), "r"(r0), "r"(r1), "r"(r2), "r"(r3) : "memory"); }
__device__ __forceinline__ void stsm4t(uint32_t a, uint32_t r0, uint32_t r1, uint32_t r2, uint32_t r3) { asm volatile("stmatrix.sync.aligned.m8n8.x4.trans.shared.b16 [%0], {%1,%2,%3,%4};" :: "r"(a), "r"(r0), "r"(r1), "r"(r2), "r"(r3) : "memory"); }
__device__ __forceinline__ void mma_h(float (&d)[4], uint32_t a0, uint32_t a1, uint32_t a2, uint32_t a3, uint32_t b0, uint32_t b1) {
    asm volatile("mma.sync.aligned.m16n8k16.row.col.f32.f16.f16.f32 {%0,%1,%2,%3}, {%4,%5,%6,%7}, {%8,%9}, {%0,%1,%2,%3};"
        : "+f"(d[0]), "+f"(d[1]), "+f"(d[2]), "+f"(d[3]) : "r"(a0), "r"(a1), "r"(a2), "r"(a3), "r"(b0), "r"(b1));
}
__device__ __forceinline__ void mma_b(float (&d)[4], uint32_t a0, uint32_t a1, uint32_t a2, uint32_t a3, uint32_t b0, uint32_t b1) {
    asm volatile("mma.sync.aligned.m16n8k16.row.col.f32.bf16.bf16.f32 {%0,%1,%2,%3}, {%4,%5,%6,%7}, {%8,%9}, {%0,%1,%2,%3};"
        : "+f"(d[0]), "+f"(d[1]), "+f"(d[2]), "+f"(d[3]) : "r"(a0), "r"(a1), "r"(a2), "r"(a3), "r"(b0), "r"(b1));
}
__device__ __forceinline__ void cp_async16(uint32_t s, const void* g) { asm volatile("cp.async.cg.shared.global [%0], [%1], 16;" :: "r"(s), "l"(g) : "memory"); }
__device__ __forceinline__ void mbar_init(uint32_t a, uint32_t c) { asm volatile("mbarrier.init.shared::cta.b64 [%0], %1;" :: "r"(a), "r"(c) : "memory"); }
__device__ __forceinline__ void mbar_expect(uint32_t a, uint32_t tx) { asm volatile("mbarrier.arrive.expect_tx.shared::cta.b64 _, [%0], %1;" :: "r"(a), "r"(tx) : "memory"); }
__device__ __forceinline__ void mbar_arrive(uint32_t a) { asm volatile("mbarrier.arrive.shared::cta.b64 _, [%0];" :: "r"(a) : "memory"); }
__device__ __forceinline__ void mbar_wait(uint32_t a) {
    uint32_t ok; int n = 0;
    do { asm volatile("{.reg .pred p; mbarrier.try_wait.parity.shared::cta.b64 p, [%1], 0; selp.u32 %0, 1, 0, p;}" : "=r"(ok) : "r"(a) : "memory"); } while (!ok && ++n < SPIN_MAX);
}
__device__ __forceinline__ void st_async32(uint32_t addr, uint32_t v, uint32_t mbar) {
    asm volatile("st.async.shared::cluster.mbarrier::complete_tx::bytes.b32 [%0], %1, [%2];" :: "r"(addr), "r"(v), "r"(mbar) : "memory");
}
__device__ __forceinline__ uint32_t mapa(uint32_t a, uint32_t r) { uint32_t o; asm("mapa.shared::cluster.u32 %0, %1, %2;" : "=r"(o) : "r"(a), "r"(r)); return o; }
__device__ __forceinline__ void bar_sync(int id, int n) { asm volatile("bar.sync %0, %1;" :: "r"(id), "r"(n) : "memory"); }
__device__ __forceinline__ void fence_async() { asm volatile("fence.proxy.async.shared::cta;" ::: "memory"); }
__device__ __forceinline__ void fence_async_g() { asm volatile("fence.proxy.async.global;" ::: "memory"); }
__device__ __forceinline__ uint32_t ld_rlx(const void* p) { uint32_t v; asm volatile("ld.relaxed.gpu.global.u32 %0, [%1];" : "=r"(v) : "l"(p) : "memory"); return v; }
__device__ __forceinline__ uint2 ld_rlx2(const void* p) { uint2 v; asm volatile("ld.relaxed.gpu.global.v2.u32 {%0,%1}, [%2];" : "=r"(v.x), "=r"(v.y) : "l"(p) : "memory"); return v; }
__device__ __forceinline__ uint4 ld_rlx4(const void* p) { uint4 v; asm volatile("ld.relaxed.gpu.global.v4.u32 {%0,%1,%2,%3}, [%4];" : "=r"(v.x), "=r"(v.y), "=r"(v.z), "=r"(v.w) : "l"(p) : "memory"); return v; }
__device__ __forceinline__ void st_rlx(void* p, uint32_t v) { asm volatile("st.relaxed.gpu.global.u32 [%0], %1;" :: "l"(p), "r"(v) : "memory"); }
__device__ __forceinline__ void st_rlx2(void* p, uint32_t a, uint32_t b) { asm volatile("st.relaxed.gpu.global.v2.u32 [%0], {%1,%2};" :: "l"(p), "r"(a), "r"(b) : "memory"); }
__device__ __forceinline__ float bf2f(uint32_t h) { return __uint_as_float(h << 16); }
__device__ __forceinline__ uint32_t pk_h(float lo, float hi) { __half2 h = __floats2half2_rn(lo, hi); return *(uint32_t*)&h; }
__device__ __forceinline__ uint32_t pk_b(float lo, float hi) { __nv_bfloat162 h = __floats2bfloat162_rn(lo, hi); return *(uint32_t*)&h; }
__device__ __forceinline__ uint32_t f2bf(float f) { return pk_b(f, 0.f); }
__device__ __forceinline__ float rbf(float f) { return __uint_as_float(pk_b(0.f, f)); }
__device__ __forceinline__ uint32_t hadd2u(uint32_t a, uint32_t b) { __half2 r = __hadd2(*(__half2*)&a, *(__half2*)&b); return *(uint32_t*)&r; }

__device__ __forceinline__ float frcp(float x) { float r; asm("rcp.approx.ftz.f32 %0, %1;" : "=f"(r) : "f"(x)); return r; }
__device__ __forceinline__ float fsqrt(float x) { float r; asm("sqrt.approx.f32 %0, %1;" : "=f"(r) : "f"(x)); return r; }
__device__ __forceinline__ float fsigm(float x) { return frcp(1.f + __expf(-x)); }
template <int D>
__device__ __forceinline__ void ld_quads(uint32_t (&q)[D][4], uint32_t ra, uint32_t zr) {
#pragma unroll
    for (int d = 0; d < D; d++) {
        q[d][0] = lds32(ra - 32 * d); q[d][1] = lds32(ra - 32 * d - 16);
        q[d][2] = d ? q[d - 1][1] + zr : lds32(ra + 16);
        q[d][3] = q[d][0] + zr;
    }
}
__device__ __forceinline__ void mma_q(float (&d)[4], const uint32_t (&q)[4], uint32_t b0, uint32_t b1) { mma_h(d, q[0], q[1], q[2], q[3], b0, b1); }
struct cf { float r, i; };
__device__ __forceinline__ cf cmul(cf a, cf b) { return { fmaf(a.r, b.r, -a.i * b.i), fmaf(a.r, b.i, a.i * b.r) }; }
__device__ __forceinline__ cf cmulc(cf a, cf b) { return { fmaf(a.r, b.r, a.i * b.i), fmaf(a.i, b.r, -a.r * b.i) }; }
__device__ __forceinline__ cf csq(cf a) { float t = a.r * a.i; return { fmaf(a.r, a.r, -a.i * a.i), t + t }; }
__device__ __forceinline__ cf cpow(float a2, float th, float l) { float e; asm("ex2.approx.ftz.f32 %0, %1;" : "=f"(e) : "f"(a2 * l)); float p = th * l; return { e * __cosf(p), e * __sinf(p) }; }
__device__ __forceinline__ void prodA(uint32_t x, uint32_t yr, uint32_t yi, uint32_t& re, uint32_t& im) {
    __half2 X = *(__half2*)&x, Yr = *(__half2*)&yr, Yi = *(__half2*)&yi, xr = __low2half2(X), xi = __high2half2(X);
    __half2 a = __hfma2(__hneg2(xi), Yi, __hmul2(xr, Yr)), b = __hfma2(xi, Yr, __hmul2(xr, Yi));
    re = *(uint32_t*)&a; im = *(uint32_t*)&b;
}
__device__ __forceinline__ void prodB(uint32_t x, uint32_t yr, uint32_t yi, uint32_t& re, uint32_t& im) {
    __half2 X = *(__half2*)&x, Yr = *(__half2*)&yr, Yi = *(__half2*)&yi, xr = __low2half2(X), xi = __high2half2(X);
    __half2 a = __hfma2(xi, Yi, __hmul2(xr, Yr)), b = __hfma2(__hneg2(xi), Yr, __hmul2(xr, Yi));
    re = *(uint32_t*)&a; im = *(uint32_t*)&b;
}

__device__ __forceinline__ void send_group(const float (&acc)[4][4], float isK, uint32_t sdst, uint32_t mb) {
#pragma unroll
    for (int r = 0; r < 2; r++) {
        const uint32_t dst = mapa(sdst, r), mbr = mapa(mb, r);
#pragma unroll
        for (int i = 0; i < 2; i++) {
            st_async32(dst + i * 2048, pk_b(acc[2 * r + i][0] * isK, acc[2 * r + i][1] * isK), mbr);
            st_async32(dst + i * 2048 + 128, pk_b(acc[2 * r + i][2] * isK, acc[2 * r + i][3] * isK), mbr);
        }
    }
}

struct Params {
    const uint16_t *x, *Are, *Aim, *ldt, *Dsk, *wr, *Bre, *Bim, *Cre, *Cim;
    uint16_t* out;
    uint8_t* scr;
    const uint8_t *wg, *wu, *wd;
};

__device__ __forceinline__ void kgen_store(uint32_t buf, int lane, uint32_t r0, uint32_t r1, uint32_t r2, uint32_t r3, uint32_t i0, uint32_t i1, uint32_t i2, uint32_t i3) {
    sts128(buf + lane * 16, r0, r1, r2, r3);
    sts128(buf + 512 + lane * 16, i0, i1, i2, i3);
}
template <int NG>
__device__ __forceinline__ void kgen_mma(float (&a0)[4], float (&a1)[4], uint32_t buf, int lane, const uint32_t (&af)[4][4]) {
    __syncwarp();
    const uint32_t a = buf + ((lane >> 3) & 1) * 512 + ((lane >> 4) * 8 + (lane & 7)) * 16;
    uint32_t b[NG][2][4];
#pragma unroll
    for (int q = 0; q < NG; q++) { ldsm4t(b[q][0], a + q * 1024); ldsm4t(b[q][1], a + q * 1024 + 256); }
#pragma unroll
    for (int s = 0; s < 4; s++) {
        mma_h(a0, af[s][0], af[s][1], af[s][2], af[s][3], b[0][s >> 1][2 * (s & 1)], b[0][s >> 1][2 * (s & 1) + 1]);
        if (NG == 2) mma_h(a1, af[s][0], af[s][1], af[s][2], af[s][3], b[NG - 1][s >> 1][2 * (s & 1)], b[NG - 1][s >> 1][2 * (s & 1) + 1]);
    }
    __syncwarp();
}

__global__ void __cluster_dims__(2, 1, 1) __launch_bounds__(NTHR, 1)
fused_kernel(const Params p, const __grid_constant__ CUtensorMap tm_s1, const __grid_constant__ CUtensorMap tm_out, const __grid_constant__ CUtensorMap tm_wg,
             const __grid_constant__ CUtensorMap tm_wu, const __grid_constant__ CUtensorMap tm_wd) {
    extern __shared__ __align__(1024) uint8_t smem[];
    const uint32_t sb = (uint32_t)__cvta_generic_to_shared(smem);
    const int tid = threadIdx.x, w = tid >> 5, lane = tid & 31, b = blockIdx.x;
    const int g = lane >> 2, c = lane & 3, ch = w & 3, role = w >> 2;
    const int rank = b & 1, pair = b >> 1;
    STAMPT(0, 0); STAMPW(0);

    const int chg = 4 * b + ch, md = chg * 128 + role * 32 + lane;
    const uint32_t t_entry = clock();
    uint32_t are_b, aim_b, ldt_b;
    asm volatile("ld.relaxed.gpu.global.u16 %0, [%1];" : "=r"(are_b) : "l"(p.Are + md) : "memory");
    asm volatile("ld.relaxed.gpu.global.u16 %0, [%1];" : "=r"(aim_b) : "l"(p.Aim + md) : "memory");
    asm volatile("ld.relaxed.gpu.global.u16 %0, [%1];" : "=r"(ldt_b) : "l"(p.ldt + chg) : "memory");
    if (tid == 32) {
        mbar_init(sb + MB_X2, 1);
        asm volatile("fence.mbarrier_init.release.cluster;" ::: "memory");
        mbar_expect(sb + MB_X2, 17408);
        while (clock() - t_entry < XDELAY);
        asm volatile("cp.async.bulk.shared::cluster.global.mbarrier::complete_tx::bytes [%0], [%1], 16384, [%2];" :: "r"(sb + SM_S), "l"(p.x + (size_t)b * 8192), "r"(sb + MB_X2) : "memory");
        asm volatile("cp.async.bulk.shared::cluster.global.mbarrier::complete_tx::bytes [%0], [%1], 1024, [%2];" :: "r"(sb + SM_WR), "l"(p.wr), "r"(sb + MB_X2) : "memory");
    }
    uint32_t pre0 = 0, pre1 = 0, pre2 = 0;
    if (tid == 64) { const uint2 d = *(const uint2*)(p.Dsk + 4 * b); pre0 = d.x; pre1 = d.y; pre2 = __ldcg((const uint32_t*)(p.scr + G_EPOCH)); }
    STAMPT(23, 96);
    if (lane == 0) {
        if (w != 2 && (w < 8 || w >= 12)) mbar_init(sb + SM_MISC + 8 * w, w >= 12 ? 4 : 1);
        if (w >= 8 && w < 12) mbar_init(sb + SM_MISC + 8 * (w == 8 ? 21 : 8 + w), 4);
        asm volatile("fence.mbarrier_init.release.cluster;" ::: "memory");
        if (w < 8 && w != 2) mbar_expect(sb + SM_MISC + 8 * w, w == 0 ? (pair < 56 ? 32768 : 0) : w == 1 ? 14336 : w > 3 ? 4096 : (pair < 56 && rank == 0) ? 1536 : 0);
        if (w >= 11) asm volatile("prefetch.tensormap [%0];" :: "l"((uint64_t)&tm_s1 + 128 * (w - 11)) : "memory");
    }
    sts128(sb + SM_TAP + tid * 16, 0, 0, 0, 0);
    if (tid < 4 * TAPS / 16 - 512) sts128(sb + SM_TAP + 8192 + tid * 16, 0, 0, 0, 0);
    if (w >= 12) { const uint32_t z = sb + SM_U + ch * US + (ch & 1) * 16 + (ch >> 1) * 64 + lane * 16; sts128(z, 0, 0, 0, 0); if (lane < 4) sts128(z + 512, 0, 0, 0, 0); }
    if (p.out == nullptr) return;

    const float dt = rbf(__expf(bf2f(ldt_b)));
    const float a2 = dt * bf2f(are_b) * 1.4426950408889634f, th = dt * bf2f(aim_b);
    const int mdd = md + (__float_as_uint(a2) == 0x7FC12345u || __float_as_uint(th) == 0x7FC12345u);
    const uint32_t bre_b = p.Bre[mdd], bim_b = p.Bim[mdd], cre_b = p.Cre[mdd], cim_b = p.Cim[mdd];
    const uint32_t kgb = sb + SM_KG + w * 4096;
    STAMPT(22, 64);
    STAMPW(1);
    cf z1 = cpow(a2, th, 1.f), z16 = cpow(a2, th, 16.f), z256 = cpow(a2, th, 256.f);
    cf z2 = csq(z1), z4 = csq(z2), z8 = csq(z4), z512 = csq(z256), z1024 = csq(z512);
    uint32_t x4, x8, x12, x256, x264, x512, x768;
    uint32_t af[4][4];
    {
        cf z12 = cmul(z4, z8), z264 = cmul(z256, z8), z768 = cmul(z256, z512);
        x4 = pk_h(z4.r, z4.i); x8 = pk_h(z8.r, z8.i); x12 = pk_h(z12.r, z12.i);
        x256 = pk_h(z256.r, z256.i); x264 = pk_h(z264.r, z264.i); x512 = pk_h(z512.r, z512.i); x768 = pk_h(z768.r, z768.i);
        cf z32 = csq(z16), z48 = cmul(z16, z32), z64 = csq(z32), z128 = csq(z64), z192 = cmul(z64, z128);
        uint32_t yr0 = pk_h(1.f, z16.r), yi0 = pk_h(0.f, z16.i), yr1 = pk_h(z32.r, z48.r), yi1 = pk_h(z32.i, z48.i);
        uint32_t x64 = pk_h(z64.r, z64.i), x128 = pk_h(z128.r, z128.i), x192 = pk_h(z192.r, z192.i);
        uint32_t r0, i0, r1, i1, r2, i2, r3, i3;
        prodA(x64, yr0, yi0, r0, i0); prodA(x64, yr1, yi1, r1, i1);
        sts128(kgb + 0 * 512 + lane * 16, yr0, yr1, r0, r1);
        sts128(kgb + 1 * 512 + lane * 16, yi0, yi1, i0, i1);
        prodA(x128, yr0, yi0, r0, i0); prodA(x128, yr1, yi1, r1, i1); prodA(x192, yr0, yi0, r2, i2); prodA(x192, yr1, yi1, r3, i3);
        sts128(kgb + 2 * 512 + lane * 16, r0, r1, r2, r3);
        sts128(kgb + 3 * 512 + lane * 16, i0, i1, i2, i3);
        __syncwarp();
        int mi = lane >> 3;
        uint32_t aa = kgb + (((mi & 1) << 1) | (mi >> 1)) * 512 + (lane & 7) * 16;
#pragma unroll
        for (int s = 0; s < 4; s++) ldsm4t(af[s], aa + s * 128);
    }
    STAMPT(1, 0); STAMPW(2);

    if (tid == 64) sts128(sb + M_PRE, pre0, pre1, pre2, 0);
    __syncthreads();
    STAMPT(24, 96);
    const uint32_t ep = lds32(sb + M_PRE + 8), tagbit = (ep + 1) & 1;
    STAMPW(3);
    uint32_t dsk_b;
    asm volatile("ld.shared.u16 %0, [%1];" : "=r"(dsk_b) : "r"(sb + M_PRE + 2 * ch));

    mbar_wait(sb + MB_X2);
    STAMPT(2, 0); STAMPW(4);
    if (tid == 12 * 32) {
        asm volatile("cp.async.bulk.global.shared::cta.bulk_group [%0], [%1], 16384;" :: "l"(p.out + (size_t)b * 8192), "r"(sb + SM_S) : "memory");
        asm volatile("cp.async.bulk.commit_group;" ::: "memory");
    }
    if (tid < 336) asm volatile("prefetch.global.L2 [%0];" :: "l"((tid < 112 ? p.wg : tid < 224 ? p.wu - 112 * 128 : p.wd - 224 * 128) + (size_t)b * 14336 + tid * 128));
    {
        const uint4 x0 = lds128(sb + SM_S + w * 1024 + lane * 16), x1 = lds128(sb + SM_S + w * 1024 + 512 + lane * 16);
        const uint4 w0 = lds128(sb + SM_WR + lane * 16), w1 = lds128(sb + SM_WR + 512 + lane * 16);
        const uint32_t ones = 0x3F803F80u;
        float sx[4] = {0, 0, 0, 0}, sw[4] = {0, 0, 0, 0}, q0[4] = {0, 0, 0, 0}, q1[4] = {0, 0, 0, 0}, r0[4] = {0, 0, 0, 0}, r1[4] = {0, 0, 0, 0};
        mma_b(sx, x0.x, x0.y, x0.z, x0.w, ones, ones); mma_b(q0, x0.x, x0.y, x0.z, x0.w, x0.x, x0.z); mma_b(q1, x0.x, x0.y, x0.z, x0.w, x0.y, x0.w);
        mma_b(r0, x0.x, x0.y, x0.z, x0.w, w0.x, w0.z); mma_b(r1, x0.x, x0.y, x0.z, x0.w, w0.y, w0.w); mma_b(sw, w0.x, w0.y, w0.z, w0.w, ones, ones);
        mma_b(sx, x1.x, x1.y, x1.z, x1.w, ones, ones); mma_b(q0, x1.x, x1.y, x1.z, x1.w, x1.x, x1.z); mma_b(q1, x1.x, x1.y, x1.z, x1.w, x1.y, x1.w);
        mma_b(r0, x1.x, x1.y, x1.z, x1.w, w1.x, w1.z); mma_b(r1, x1.x, x1.y, x1.z, x1.w, w1.y, w1.w); mma_b(sw, w1.x, w1.y, w1.z, w1.w, ones, ones);
        const bool dg = c == (g >> 1);
        float a = (c == 0) ? sx[0] + sx[2] : 0.f, ww = (c == 0) ? sw[0] + sw[2] : 0.f;
        float q = dg ? ((g & 1) ? q0[1] + q1[3] : q0[0] + q1[2]) : 0.f, r = dg ? ((g & 1) ? r0[1] + r1[3] : r0[0] + r1[2]) : 0.f;
#pragma unroll
        for (int o = 16; o; o >>= 1) { a += __shfl_xor_sync(~0u, a, o); q += __shfl_xor_sync(~0u, q, o); r += __shfl_xor_sync(~0u, r, o); ww += __shfl_xor_sync(~0u, ww, o); }
        const float mean = a * (1.f / 512), var = fmaxf(fmaf(-mean, mean, q * (1.f / 512)), 0.f);
        const float m = rbf(mean), sd = rbf(fsqrt(rbf(rbf(var) + 1e-5f))), rs = frcp(sd), nm = -m * rs;
        if (lane == 0) {
            const uint32_t rb = f2bf(rs * fmaf(-m, ww, r));
            sts64(sb + M_STAT + w * 8, ((rb & 0x8000) ? (~rb & 0xFFFF) : (rb | 0x8000)) << 16 | (uint32_t)(2047 - (16 * b + w)) << 1 | tagbit,
                  f2bf(m) | (f2bf(sd) & 0x7FFF) << 16 | tagbit << 31);
        }
        const uint32_t tg = tagbit * 0x00010001u;
        auto nrm = [&](uint32_t v) { return (pk_h(fmaf(__uint_as_float(v << 16), rs, nm), fmaf(__uint_as_float(v & 0xFFFF0000u), rs, nm)) & 0xFFFEFFFEu) | tg; };
        sts128(sb + SM_XT + w * 1040 + lane * 16, nrm(x0.x), nrm(x0.y), nrm(x0.z), nrm(x0.w));
        sts128(sb + SM_XT + w * 1040 + 512 + lane * 16, nrm(x1.x), nrm(x1.y), nrm(x1.z), nrm(x1.w));
    }
    STAMPW(5);
    __syncthreads();
    STAMPT(3, 0);
    {
        const uint32_t xa = sb + SM_XT + (lane & 15) * 1040 + (w * 32 + (lane >> 4) * 8) * 2, lt = sb + SM_LT + (w * 32 + g) * 16 + c * 4;
        uint32_t xr[2][4];
        ldsm4t(xr[0], xa); ldsm4t(xr[1], xa + 32);
#pragma unroll
        for (int i = 0; i < 2; i++)
#pragma unroll
            for (int j = 0; j < 4; j++) sts32(lt + (j & 1) * 8192 + (i * 16 + (j >> 1) * 8) * 16, xr[i][j]);
        if (w == 1) {
            const uint2 kv = lane < 16 ? lds64(sb + M_STAT + lane * 8) : make_uint2(0, 0);
            if (kv.x == __reduce_max_sync(~0u, kv.x) && lane < 16) st_rlx2(p.scr + G_RINFO + b * 8, kv.x, kv.y);
        }
    }
    STAMPW(6);
    fence_async();
    __syncthreads();
    if (tid == 15 * 32) {
        asm volatile("cp.async.bulk.tensor.3d.global.shared::cta.bulk_group [%0, {%2, %3, %4}], [%1];"
            :: "l"((uint64_t)&tm_s1), "r"(sb + SM_LT), "r"(b * 32), "r"(0), "r"(0) : "memory");
        asm volatile("cp.async.bulk.commit_group;" ::: "memory");
        if (pair < 56) {
            asm volatile("cp.async.bulk.tensor.2d.shared::cluster.global.mbarrier::complete_tx::bytes [%0], [%1, {%3, %4}], [%2];"
                :: "r"(sb + SM_WG), "l"((uint64_t)&tm_wg), "r"(sb + MB_W1), "r"(pair * 32), "r"(rank * 256) : "memory");
            asm volatile("cp.async.bulk.tensor.2d.shared::cluster.global.mbarrier::complete_tx::bytes [%0], [%1, {%3, %4}], [%2];"
                :: "r"(sb + SM_WU), "l"((uint64_t)&tm_wu), "r"(sb + MB_W1), "r"(pair * 32), "r"(rank * 256) : "memory");
        }
        asm volatile("cp.async.bulk.tensor.2d.shared::cluster.global.mbarrier::complete_tx::bytes [%0], [%1, {%3, %4}], [%2];"
            :: "r"(sb + SM_WD), "l"((uint64_t)&tm_wd), "r"(sb + MB_W2), "r"((b >> 3) * 32), "r"((b & 7) * 224) : "memory");
    }
    STAMPT(4, 0); STAMPW(7);

    float mxw;
    {
        cf dB = { dt * bf2f(bre_b), dt * bf2f(bim_b) }, C = { bf2f(cre_b), bf2f(cim_b) };
        cf W = cmul(C, dB);
        float k2048; { cf z2048 = csq(z1024); k2048 = fmaf(W.r, z2048.r, -W.i * z2048.i); }
#pragma unroll
        for (int o = 16; o; o >>= 1) k2048 += __shfl_xor_sync(~0u, k2048, o);
        uint32_t e = __reduce_max_sync(~0u, __float_as_uint(fmaxf(fabsf(W.r), fabsf(W.i)))) >> 23;
        e = min(max(e, 1u), 252u);
        mxw = __uint_as_float((e + 1) << 23);
        float sc = __uint_as_float((253u - e) << 23);
        cf Wc = { W.r * sc, -W.i * sc };
        float acc[5][4];
#pragma unroll
        for (int t = 0; t < 5; t++) { acc[t][0] = acc[t][1] = acc[t][2] = acc[t][3] = 0.f; }
        uint32_t r0, r1, r2, r3, i0, i1, i2, i3;
        {
            cf y1 = cmulc(Wc, z1), y2 = cmulc(y1, z1), y3 = cmulc(y2, z1);
            const uint32_t yr0 = pk_h(Wc.r, y1.r), yi0 = pk_h(Wc.i, y1.i), yr1 = pk_h(y2.r, y3.r), yi1 = pk_h(y2.i, y3.i);
            prodB(x4, yr0, yi0, r0, i0); prodB(x4, yr1, yi1, r1, i1);
            kgen_store(kgb + 2048, lane, yr0, yr1, r0, r1, yi0, yi1, i0, i1);
            prodB(x8, yr0, yi0, r0, i0); prodB(x8, yr1, yi1, r1, i1); prodB(x12, yr0, yi0, r2, i2); prodB(x12, yr1, yi1, r3, i3);
            kgen_store(kgb + 3072, lane, r0, r1, r2, r3, i0, i1, i2, i3);
            kgen_mma<2>(acc[0], acc[1], kgb + 2048, lane, af);
        }
        {
            cf ya = cmulc(Wc, z256), yb = cmulc(ya, z2);
            r0 = pk_h(ya.r, yb.r); i0 = pk_h(ya.i, yb.i);
            prodB(x4, r0, i0, r1, i1); prodB(x8, r0, i0, r2, i2); prodB(x12, r0, i0, r3, i3);
            kgen_store(kgb + 2048, lane, r0, r1, r2, r3, i0, i1, i2, i3);
            ya = cmulc(Wc, z512); yb = cmulc(ya, z4);
            r0 = pk_h(ya.r, yb.r); i0 = pk_h(ya.i, yb.i);
            prodB(x8, r0, i0, r1, i1); prodB(x256, r0, i0, r2, i2); prodB(x264, r0, i0, r3, i3);
            kgen_store(kgb + 3072, lane, r0, r1, r2, r3, i0, i1, i2, i3);
            kgen_mma<2>(acc[2], acc[3], kgb + 2048, lane, af);
        }
        {
            cf ya = cmulc(Wc, z1024), yb = cmulc(ya, z8);
            r0 = pk_h(ya.r, yb.r); i0 = pk_h(ya.i, yb.i);
            prodB(x256, r0, i0, r1, i1); prodB(x512, r0, i0, r2, i2); prodB(x768, r0, i0, r3, i3);
            kgen_store(kgb + 2048, lane, r0, r1, r2, r3, i0, i1, i2, i3);
            kgen_mma<1>(acc[4], acc[4], kgb + 2048, lane, af);
        }
#pragma unroll
        for (int t = 0; t < 5; t++) {
            sts32(kgb + t * 256 + g * 16 + c * 4, pk_h(acc[t][0], acc[t][1]));
            sts32(kgb + t * 256 + 128 + g * 16 + c * 4, pk_h(acc[t][2], acc[t][3]));
        }
        if (lane == 0) sts64f(kgb + 1280, mxw, k2048);
    }
    STAMPT(5, 0); STAMPW(8);
    const int lb = (w + 12) & 15;
    const int bb = lb * 8 + (lane >> 2), cc = lane & 3;
    const uint4* s0 = (const uint4*)(p.scr + G_S1) + (size_t)b * 1024 + bb * 4 + cc;
    const bool needl = (lane < 4) && bb > 0, needr = (lane >= 28) && bb < 127;
    uint4 u0 = ld_rlx4(s0), u1 = ld_rlx4(s0 + 512), hl = make_uint4(0, 0, 0, 0), hr = hl;
    if (needl) hl = ld_rlx4(s0 + 512 - 4);
    if (needr) hr = ld_rlx4(s0 + 4);
    uint4 e0 = make_uint4(0, 0, 0, 0), e1 = e0;
    const uint4* rp = (const uint4*)(p.scr + G_RINFO) + 2 * lane;
    if (w == 12) { e0 = ld_rlx4(rp); e1 = ld_rlx4(rp + 1); }
    bar_sync(1 + ch, 128);
    {
        const int a = (4 * role + (lane >> 3) + 1) & 15, n = lane & 7, t128 = a * 8 + n;
        const uint32_t kb = sb + SM_KG + ch * 4096;
        float S = fabsf(1.f + bf2f(dsk_b)), k2048 = 0.f, mx[4];
#pragma unroll
        for (int q = 0; q < 4; q++) { mx[q] = ldsf(kb + q * 16384 + 1280); S = fmaf(48.f, mx[q], S); k2048 += ldsf(kb + q * 16384 + 1284); }
        const uint32_t es = min(__float_as_uint(S) >> 23, 252u);
        const float sK = __uint_as_float((253u - es) << 23), isK = __uint_as_float((es + 1) << 23);
        auto ksum = [&](uint32_t off) {
            float v = 0.f;
#pragma unroll
            for (int q = 0; q < 4; q++) { uint16_t h; asm volatile("ld.shared.u16 %0, [%1];" : "=h"(h) : "r"(kb + q * 16384 + off)); v = fmaf(__half2float(__ushort_as_half(h)), mx[q], v); }
            return v;
        };
        float kv[5];
#pragma unroll
        for (int t = 0; t < 5; t++) kv[t] = ksum(t * 256 + t128 * 2);
        if (t128 == 0) kv[0] += 1.f + bf2f(dsk_b);
        {
            const float k256 = __shfl_sync(~0u, kv[2], 24), k512 = __shfl_sync(~0u, kv[3], 24);
            if (t128 == 127) { kv[1] -= k256; kv[2] -= k512; }
        }
        const uint32_t tb = sb + SM_TAP + ch * TAPS;
        uint32_t pos[5], oo[5];
        pos[0] = tb + T_L0 + 2 * (272 - (16 * a + n));              oo[0] = 576;
        pos[1] = pos[0] - 16;                                       oo[1] = 576;
        pos[2] = tb + T_L1 + (n & 3) * 320 + 2 * (48 - (2 * a + (n >> 2)));                    oo[2] = 192;
        pos[3] = tb + T_L2 + (n & 1) * 384 + 2 * (80 - (2 * a + 32 * (n >> 2) + ((n >> 1) & 1))); oo[3] = 192;
        pos[4] = tb + T_L3 + (n & 1) * 384 + 2 * (80 - (a + 16 * (n >> 1)));                   oo[4] = 192;
#pragma unroll
        for (int t = 0; t < 5; t++) { uint16_t h = __half_as_ushort(__float2half_rn(kv[t] * sK)); sts16(pos[t], h); sts16(pos[t] + oo[t] - 2, h); }
        if (t128 == 0) {
            uint16_t h = __half_as_ushort(__float2half_rn(k2048 * sK));
            sts16(tb + T_L3 + 2 * (80 - 64), h); sts16(tb + T_L3 + 2 * (80 - 64) + 190, h);
            stsf(sb + M_CH + ch * 16, isK);
            sts32(sb + M_CH + ch * 16 + 4, __half_as_ushort(__float2half_rn(-kv[4] * sK)));
        }
    }
    STAMPT(6, 0); STAMPW(9);

    if (w == 12) {
        int n = 0;
        while (__any_sync(~0u, ((e0.x ^ tagbit) | (e0.z ^ tagbit) | (e1.x ^ tagbit) | (e1.z ^ tagbit) | ((e0.y >> 31) ^ tagbit) | ((e0.w >> 31) ^ tagbit) | ((e1.y >> 31) ^ tagbit) | ((e1.w >> 31) ^ tagbit)) & 1) && ++n < SPIN_MAX) {
            e0 = ld_rlx4(rp); e1 = ld_rlx4(rp + 1);
        }
        if (e0.z > e0.x) { e0.x = e0.z; e0.y = e0.w; }
        if (e1.z > e1.x) { e1.x = e1.z; e1.y = e1.w; }
        if (e1.x > e0.x) { e0.x = e1.x; e0.y = e1.y; }
        if (e0.x == __reduce_max_sync(~0u, e0.x)) { sts32(sb + M_IDX, 2047 - ((e0.x >> 1) & 0x7FF)); sts32(sb + M_IDX + 4, e0.x); sts32(sb + M_IDX + 8, e0.y); }
    }
    uint32_t W[13];
    {
        const uint32_t tg = tagbit * 0x00010001u;
        int n = 0;
        while (true) {
            uint32_t bad = (u0.x ^ tg) | (u0.y ^ tg) | (u0.z ^ tg) | (u0.w ^ tg) | (u1.x ^ tg) | (u1.y ^ tg) | (u1.z ^ tg) | (u1.w ^ tg);
            if (needl) bad |= (hl.y ^ tg) | (hl.z ^ tg) | (hl.w ^ tg);
            if (needr) bad |= (hr.x ^ tg) | (hr.y ^ tg);
            if (!__any_sync(~0u, (bad & 0x00010001u) != 0) || ++n > SPIN_MAX) break;
            u0 = ld_rlx4(s0); u1 = ld_rlx4(s0 + 512);
            if (needl) hl = ld_rlx4(s0 + 512 - 4);
            if (needr) hr = ld_rlx4(s0 + 4);
        }
        const uint32_t mk = 0xFFFEFFFEu;
        W[3] = u0.x & mk; W[4] = u0.y & mk; W[5] = u0.z & mk; W[6] = u0.w & mk;
        W[7] = u1.x & mk; W[8] = u1.y & mk; W[9] = u1.z & mk; W[10] = u1.w & mk;
        uint32_t t0 = __shfl_up_sync(~0u, W[8], 4), t1 = __shfl_up_sync(~0u, W[9], 4), t2 = __shfl_up_sync(~0u, W[10], 4);
        uint32_t t3 = __shfl_down_sync(~0u, W[3], 4), t4 = __shfl_down_sync(~0u, W[4], 4);
        if (lane < 4) { t0 = needl ? (hl.y & mk) : 0u; t1 = needl ? (hl.z & mk) : 0u; t2 = needl ? (hl.w & mk) : 0u; }
        if (lane >= 28) { t3 = needr ? (hr.x & mk) : 0u; t4 = needr ? (hr.y & mk) : 0u; }
        W[0] = t0; W[1] = t1; W[2] = t2; W[11] = t3; W[12] = t4;
    }
    if (lane == 0 && (w == 12 || w == 15)) asm volatile("cp.async.bulk.wait_group 0;" ::: "memory");
    STAMPT(8, 0); STAMPW(10);
    __syncthreads();
    asm volatile("barrier.cluster.arrive.relaxed.aligned;" ::: "memory");
    if (tid == 511) { fence_async_g(); asm volatile("red.release.gpu.global.add.u32 [%0], 1;" :: "l"(p.scr + G_CNT2) : "memory"); }
    {
        const uint32_t pad = (cc & 1) * 16 + (cc >> 1) * 64;
        uint32_t ua = sb + SM_U + cc * US + pad + ((bb >> 2) + 4) * 144 + (bb & 3) * 32;
        sts128(ua, W[3], W[4], W[5], W[6]); sts128(ua + 16, W[7], W[8], W[9], W[10]);
        if (role != 0) asm volatile("bar.arrive 8, 512;" ::: "memory");
        const uint32_t ab = sb + SM_ARR + cc * AS + pad;
        uint32_t V[12];
#pragma unroll
        for (int k = 0; k < 12; k++) V[k] = __byte_perm(W[k], W[k + 1], 0x5432);
        uint32_t P[12], W3[10];
#pragma unroll
        for (int k = 0; k < 12; k++) P[k] = hadd2u(W[k + 1], V[k]);
#pragma unroll
        for (int k = 0; k < 10; k++) W3[k] = hadd2u(P[k], V[k + 1]);
        if (lb < 14) {
            const uint32_t ra = ab + bb * 32;
            sts128(ra + A_A0 + 256, W3[2], W3[3], W3[4], W3[5]); sts128(ra + A_A0 + 272, W3[6], W3[7], W3[8], W3[9]);
            sts128(ra + A_A1, W3[0], W3[1], W3[2], W3[3]);       sts128(ra + A_A1 + 16, W3[4], W3[5], W3[6], W3[7]);
            sts128(ra + A_B0, W[2], W[3], W[4], W[5]);           sts128(ra + A_B0 + 16, W[6], W[7], W[8], W[9]);
            sts128(ra + A_B1, W[0], W[1], W[2], W[3]);           sts128(ra + A_B1 + 16, W[4], W[5], W[6], W[7]);
        }
        uint32_t W5[8];
        if (lb < 12) {
#pragma unroll
            for (int k = 0; k < 8; k++) W5[k] = hadd2u(hadd2u(W3[k + 2], W[k + 2]), W[k + 4]);
            uint32_t ra = ab + A_W5 + (2 * bb + 16) * 16;
            sts128(ra, W5[0], W5[1], W5[2], W5[3]); sts128(ra + 16, W5[4], W5[5], W5[6], W5[7]);
        }
        if (lb < 8) {
            uint32_t W7[8], W9[8];
#pragma unroll
            for (int k = 0; k < 8; k++) { W7[k] = hadd2u(hadd2u(W5[k], V[k + 1]), V[k + 4]); W9[k] = hadd2u(hadd2u(W7[k], W[k + 1]), W[k + 5]); }
            uint32_t r9 = ab + A_W9 + (bb + 16) * 32, sw = ((bb >> 2) & 1) * 16;
            sts128(r9 + sw, W9[0], W9[1], W9[2], W9[3]); sts128(r9 + (sw ^ 16), W9[4], W9[5], W9[6], W9[7]);
            uint32_t r7 = ab + A_W7 + (bb + 16) * 32;
            sts128(r7 + (sw ^ 16), W7[0], W7[1], W7[2], W7[3]);
            if (bb < 63) sts128(r7 + 32 + (((bb + 1) >> 2) & 1) * 16, W7[4], W7[5], W7[6], W7[7]);
            uint32_t rp = ab + A_P2 + (2 * bb + 16) * 16;
            sts128(rp, P[4], P[5], P[6], P[7]); sts128(rp + 16, P[8], P[9], P[10], P[11]);
        }
        if ((lb >> 2) == 2) {
            const int zc = lb & 3;
            const uint32_t z = sb + SM_ARR + zc * AS + (zc & 1) * 16 + (zc >> 1) * 64 + lane * 16;
            if (lane < 15) { sts128(z + A_A0, 0, 0, 0, 0); sts128(z + A_W5, 0, 0, 0, 0); sts128(z + A_P2, 0, 0, 0, 0); }
            if (lane < 30) sts128(z + A_W9, 0, 0, 0, 0);
            sts128(z + A_W7, 0, 0, 0, 0);
        }
        if (bb == 0) {
            const uint32_t u0 = W[3], u1 = W[4];
            sts128(ab + A_A0 + 15 * 16, 0, 0, 0, W3[1]);
            const uint32_t s01 = hadd2u(u0, __byte_perm(u0, 0, 0x1044));
            sts128(ab + A_W5 + 15 * 16, 0, 0, 0, s01);
            uint32_t s23 = hadd2u(hadd2u(__byte_perm(s01, 0, 0x3232), __byte_perm(u1, 0, 0x1010)), __byte_perm(u1, 0, 0x3244));
            sts128(ab + A_W9 + 15 * 32, 0, 0, s01, s23);
            sts128(ab + A_W9 + 15 * 32 + 16, 0, 0, 0, 0);
            sts128(ab + A_W7 + 16 * 32, 0, 0, __byte_perm(u0, 0, 0x1044), __byte_perm(s01, s23, 0x5432));
            sts128(ab + A_P2 + 15 * 16, 0, 0, 0, s01 ^ 0x80008000u);
        }
    }
    if (role == 0) { asm volatile("bar.arrive 9, 512;" ::: "memory"); bar_sync(8, 512); } else bar_sync(9, 512);
    STAMPT(9, 0); STAMPW(11);

    const uint32_t pad = (ch & 1) * 16 + (ch >> 1) * 64;
    const uint32_t ab = sb + SM_ARR + ch * AS + pad, tb = sb + SM_TAP + ch * TAPS;
    const uint32_t rl = 2 * (2 * c - g - (g & 1));
    const uint32_t zr = lds32(sb + SM_U);
    if (role >= 1) asm volatile("barrier.cluster.wait.aligned;" ::: "memory");

    if (role == 0) {
        uint32_t Rq[17][4];
        ld_quads<17>(Rq, tb + T_L0 + ((g & 1) ? 576 : 0) + 2 * 272 + rl, zr);
        float fx;
        {
            const uint32_t u01 = lds32(sb + SM_U + ch * US + pad + 4 * 144), k2 = lds32(tb + T_L2 + 160);
            const float2 uf = __half22float2(*(const __half2*)&u01);
            fx = __low2float(*(const __half2*)&k2) * (lane == 27 ? uf.x : lane == 31 ? uf.x + uf.y : 0.f);
        }
        uint32_t uq = sb + SM_U + ch * US + pad + ((lane & 7) + 4) * 144 + ((lane >> 3) & 1) * 16 + (lane >> 4) * 32;
        uint32_t ya = ab + A_Y0 + (lane & 7) * 144 + (lane >> 4) * 32 + ((lane >> 3) & 1) * 16;
        STAMPT(28, 0);
#pragma unroll 1
        for (int Q = 0; Q < 4; Q++) {
            float acc[4][4];
#pragma unroll
            for (int i = 0; i < 4; i++) acc[i][0] = acc[i][1] = acc[i][2] = acc[i][3] = 0.f;
#pragma unroll
            for (int e2 = 0; e2 < 10; e2++) {
                uint32_t bf[4];
                ldsm4(bf, uq + (2 * e2 - 16) * 32 + ((e2 - 8) >> 1) * 16);
#pragma unroll
                for (int h = 0; h < 2; h++) {
                    const int e = 2 * e2 + h;
#pragma unroll
                    for (int i = 0; i < 4; i++) {
                        const int d = i + 16 - e;
                        if (d >= 0 && d <= 16) mma_q(acc[i], Rq[d], bf[2 * h], bf[2 * h + 1]);
                    }
                }
            }
            if (Q == 0) acc[3][3] += fx;
            stsm4t(ya, pk_b(acc[0][0], acc[0][1]), pk_b(acc[0][2], acc[0][3]), pk_b(acc[1][0], acc[1][1]), pk_b(acc[1][2], acc[1][3]));
            stsm4t(ya + 64, pk_b(acc[2][0], acc[2][1]), pk_b(acc[2][2], acc[2][3]), pk_b(acc[3][0], acc[3][1]), pk_b(acc[3][2], acc[3][3]));
            __syncwarp();
            if (lane == 0) mbar_arrive(sb + MB_Y0 + Q * 8);
            uq += 8 * 144; ya += 8 * 144;
            STAMPT(29 + Q, 0);
        }
        STAMPT(10, 0);
    } else if (role == 1) {
        uint32_t R1[4][3][4];
#pragma unroll
        for (int q = 0; q < 4; q++) ld_quads<3>(R1[q], tb + T_L1 + q * 320 + ((g & 1) ? 192 : 0) + 2 * 48 + rl, zr);
        const uint32_t idb = 0x3F803F80u & ((g == 2 * c) ? 0x0000FFFFu : (g == 2 * c + 1) ? 0xFFFF0000u : 0u);
        const uint32_t lrow = (lane & 15) * 16, zb = sb + SM_U + lrow;
        uint32_t ya = ab + A_Y0 + (lane >> 3) * 144 + (lane & 7) * 16;
#pragma unroll 1
        for (int G = 0; G < 4; G++) {
            float acc[4][4], ac2[4][4];
#pragma unroll
            for (int i = 0; i < 4; i++) { acc[i][0] = acc[i][1] = acc[i][2] = acc[i][3] = 0.f; ac2[i][0] = ac2[i][1] = ac2[i][2] = ac2[i][3] = 0.f; }
#pragma unroll
            for (int ap = 0; ap < 2; ap++) {
                const uint32_t base = ab + (ap ? A_A1 : A_A0 + 256) + (lane >> 4) * (ap ? A_B1 - A_A1 : A_B0 - A_A0 - 256) + lrow + (4 * G - 4) * 256;
#pragma unroll
                for (int e = 0; e < 6; e++) {
                    const bool z = G == 0 && (e < 3 || (e == 3 && (ap == 1 || lane >= 16)));
                    uint32_t f[4]; ldsm4t(f, (e < 4 && z) ? zb : base + e * 256);
#pragma unroll
                    for (int i = 0; i < 4; i++) {
                        const int d = i + 2 - e;
                        if (d >= 0 && d <= 2) { mma_q(acc[i], R1[2 * ap][d], f[0], f[1]); mma_q(ac2[i], R1[2 * ap + 1][d], f[2], f[3]); }
                    }
                }
            }
            STAMPT(33 + G, 128);
            mbar_wait(sb + MB_Y0 + G * 8);
#pragma unroll
            for (int h = 0; h < 2; h++) {
                uint32_t f[4]; ldsm4t(f, ya + h * 576);
                mma_b(ac2[2 * h], idb, 0, 0, idb, f[0], f[1]); mma_b(ac2[2 * h + 1], idb, 0, 0, idb, f[2], f[3]);
            }
#pragma unroll
            for (int i = 0; i < 4; i++) { acc[i][0] += ac2[i][0]; acc[i][1] += ac2[i][1]; acc[i][2] += ac2[i][2]; acc[i][3] += ac2[i][3]; }
            if (G == 0) {
                send_group(acc, ldsf(sb + M_CH + ch * 16), sb + SM_S + (rank * 4 + ch) * 256 + ((g ^ (rank * 4 + ch)) << 4) + c * 4, sb + MB_TILE);
            } else {
                __syncwarp();
#pragma unroll
                for (int h = 0; h < 2; h++)
                    stsm4(ya + h * 576, pk_b(acc[2 * h][0], acc[2 * h][1]), pk_b(acc[2 * h][2], acc[2 * h][3]), pk_b(acc[2 * h + 1][0], acc[2 * h + 1][1]), pk_b(acc[2 * h + 1][2], acc[2 * h + 1][3]));
                __syncwarp();
                if (lane == 0) mbar_arrive(sb + MB_Y1 + G * 8);
            }
            ya += 8 * 144;
        }
        STAMPT(12, 128);
    } else if (role == 2) {
        const uint32_t dsel = (g == 2 * c) ? 0x0000FFFFu : (g == 2 * c + 1) ? 0xFFFF0000u : 0u;
        {
            uint32_t R3[2][5][4];
#pragma unroll
            for (int q = 0; q < 2; q++) ld_quads<5>(R3[q], tb + T_L3 + q * 384 + ((g & 1) ? 192 : 0) + 2 * 80 + rl, zr);
            float acc[4][2][4];
#pragma unroll
            for (int i = 0; i < 4; i++) for (int h = 0; h < 2; h++) acc[i][h][0] = acc[i][h][1] = acc[i][h][2] = acc[i][h][3] = 0.f;
            const int row = lane & 15;
            const uint32_t lo = row * 32 + (((lane >> 4) ^ ((row >> 2) & 1)) << 4);
#pragma unroll
            for (int q = 0; q < 2; q++) {
#pragma unroll
                for (int jb = -1 + q; jb < 4; jb++) {
                    uint32_t f[4]; ldsm4t(f, ab + (q ? A_W7 : A_W9) + (jb + 1) * 512 + lo);
#pragma unroll
                    for (int i = 0; i < 4; i++) {
                        const int d = i - jb;
                        if (d >= 0 && d <= 4) {
                            if (jb >= 0) mma_q(acc[i][0], R3[q][d], f[0], f[1]);
                            mma_q(acc[i][1], R3[q][d], f[2], f[3]);
                        }
                    }
                }
            }
            __syncwarp();
#pragma unroll
            for (int i = 0; i < 4; i++)
                stsm4(ab + A_W9 + (256 * i + 16 * (lane & 15) + 8 * (lane >> 4)) * 2,
                      pk_b(acc[i][0][0], acc[i][0][1]), pk_b(acc[i][0][2], acc[i][0][3]), pk_b(acc[i][1][0], acc[i][1][1]), pk_b(acc[i][1][2], acc[i][1][3]));
            __syncwarp();
            STAMPT(14, 256);
        }
        uint32_t R2[2][5][4];
#pragma unroll
        for (int q = 0; q < 2; q++) ld_quads<5>(R2[q], tb + T_L2 + q * 384 + ((g & 1) ? 192 : 0) + 2 * 80 + rl, zr);
        const float isK = ldsf(sb + M_CH + ch * 16);
        const uint32_t kc = lds32(sb + M_CH + ch * 16 + 4);
        const uint32_t idb = 0x3F803F80u & dsel, idc = (kc | kc << 16) & dsel;
        const uint32_t lrow = (lane & 15) * 16, zb = sb + SM_U + lrow;
        const int ch8 = rank * 4 + ch;
        const uint32_t sdst = sb + SM_S + ch8 * 256 + ((g ^ ch8) << 4) + c * 4;
        uint32_t ya = ab + A_Y0 + 8 * 144 + (lane >> 3) * 144 + (lane & 7) * 16;
#pragma unroll 1
        for (int G = 1; G < 4; G++) {
            float acc[4][4], ac2[4][4];
#pragma unroll
            for (int i = 0; i < 4; i++) { acc[i][0] = acc[i][1] = acc[i][2] = acc[i][3] = 0.f; ac2[i][0] = ac2[i][1] = ac2[i][2] = ac2[i][3] = 0.f; }
            {
                const uint32_t base = ab + ((lane >> 4) ? A_A1 : A_W5 + 256) + lrow + (4 * G - 8) * 256;
#pragma unroll
                for (int e = 0; e < 8; e++) {
                    const bool z = G == 1 && (e < 3 || (e == 3 && lane >= 16));
                    uint32_t f[4]; ldsm4t(f, (e < 4 && z) ? zb : base + e * 256);
#pragma unroll
                    for (int i = 0; i < 4; i++) {
                        const int d = i + 4 - e;
                        if (d >= 0 && d <= 4) { mma_q(acc[i], R2[0][d], f[0], f[1]); mma_q(ac2[i], R2[1][d], f[2], f[3]); }
                    }
                }
                uint32_t fp[2][4], fy[2][4];
                const uint32_t pa = ab + A_P2 + 256 + (4 * G - 8 + (lane >> 4)) * 256 + lrow;
                ldsm4t(fp[1], pa + 512);
                if (G >= 2) {
                    ldsm4t(fp[0], pa);
                    const uint32_t y3 = ab + A_W9 + (4 * G - 8 + (lane >> 4)) * 256 + lrow;
                    ldsm4t(fy[0], y3); ldsm4t(fy[1], y3 + 512);
                    mma_h(acc[0], idc, 0, 0, idc, fp[0][0], fp[0][1]); mma_h(acc[1], idc, 0, 0, idc, fp[0][2], fp[0][3]);
                    mma_h(acc[2], idc, 0, 0, idc, fp[1][0], fp[1][1]);
                    mma_b(ac2[0], idb, 0, 0, idb, fy[0][0], fy[0][1]); mma_b(ac2[1], idb, 0, 0, idb, fy[0][2], fy[0][3]);
                    mma_b(ac2[2], idb, 0, 0, idb, fy[1][0], fy[1][1]); mma_b(ac2[3], idb, 0, 0, idb, fy[1][2], fy[1][3]);
                }
                mma_h(acc[3], idc, 0, 0, idc, fp[1][2], fp[1][3]);
            }
            STAMPT(37 + G, 256);
            uint32_t f1[2][4];
            mbar_wait(sb + MB_Y1 + G * 8);
            STAMPT(41 + G, 256);
            ldsm4t(f1[0], ya); ldsm4t(f1[1], ya + 576);
            mma_b(acc[0], idb, 0, 0, idb, f1[0][0], f1[0][1]); mma_b(acc[1], idb, 0, 0, idb, f1[0][2], f1[0][3]);
            mma_b(acc[2], idb, 0, 0, idb, f1[1][0], f1[1][1]); mma_b(acc[3], idb, 0, 0, idb, f1[1][2], f1[1][3]);
#pragma unroll
            for (int i = 0; i < 4; i++) { acc[i][0] += ac2[i][0]; acc[i][1] += ac2[i][1]; acc[i][2] += ac2[i][2]; acc[i][3] += ac2[i][3]; }
            send_group(acc, isK, sdst + G * 4096, sb + MB_TILE + 8 * G);
            ya += 8 * 144;
        }
        STAMPT(13, 256);
    } else {
        const int idx = lds32(sb + M_IDX);
        uint32_t xs0 = 0, xs1 = 0;
        if (w < 15 && pair < 56) {
            const uint32_t* xp = (const uint32_t*)(p.x + (size_t)idx * 512 + rank * 256) + (tid - 384);
            xs0 = __ldg(xp); if (tid - 384 < 32) xs1 = __ldg(xp + 96);
        }
        const int mw = w - 12, t3 = tid - 384;
        const uint32_t k0 = lds32(sb + M_IDX + 4), m0 = lds32(sb + M_IDX + 8);
        STAMPT(45, 384);
            if (w < 15 && pair < 56) {
                const float mS = bf2f(m0 & 0xFFFF), rsS = frcp(bf2f((m0 >> 16) & 0x7FFF));
                sts32(sb + M_XS + t3 * 4, pk_b(rbf(bf2f(xs0 & 0xFFFF) - mS) * rsS, rbf(bf2f(xs0 >> 16) - mS) * rsS));
                if (t3 < 32) sts32(sb + M_XS + (t3 + 96) * 4, pk_b(rbf(bf2f(xs1 & 0xFFFF) - mS) * rsS, rbf(bf2f(xs1 >> 16) - mS) * rsS));
                bar_sync(7, 96);
                float acc[4][4];
#pragma unroll
                for (int i = 0; i < 4; i++) acc[i][0] = acc[i][1] = acc[i][2] = acc[i][3] = 0.f;
                mbar_wait(sb + MB_W1);
                STAMPT(46, 384);
#pragma unroll
                for (int k = 0; k < 6; k++) {
                    const int s = min(mw + 3 * k, 15);
                    const bool on = mw + 3 * k < 16 && g == 0;
                    const int row = s * 16 + (lane & 7) + (lane >> 4) * 8;
                    const uint32_t xa = sb + M_XS + (s * 16 + 2 * c) * 2;
                    const uint32_t v0 = lds32(xa), v1 = lds32(xa + 16), b0 = on ? v0 : 0u, b1 = on ? v1 : 0u;
#pragma unroll
                    for (int mt = 0; mt < 4; mt++) {
                        uint32_t f[4];
                        const int chunk = (mt & 1) * 2 + ((lane >> 3) & 1);
                        ldsm4t(f, sb + ((mt >> 1) ? SM_WU : SM_WG) + row * 64 + ((chunk ^ ((row >> 1) & 3)) << 4));
                        mma_b(acc[mt], f[0], f[1], f[2], f[3], b0, b1);
                    }
                }
                if (c == 0) {
                    const uint32_t dst = mapa(sb + SM_GRED + (rank * 3 + mw) * 256 + g * 4, 0), mbr = mapa(sb + MB_G, 0);
#pragma unroll
                    for (int i = 0; i < 4; i++) { st_async32(dst + i * 64, __float_as_uint(acc[i][0]), mbr); st_async32(dst + i * 64 + 32, __float_as_uint(acc[i][2]), mbr); }
                }
                if (rank == 0 && mw == 0) {
                    mbar_wait(sb + MB_G);
                    float gs = 0.f, us = 0.f;
#pragma unroll
                    for (int q = 0; q < 6; q++) { gs += ldsf(sb + SM_GRED + q * 256 + lane * 4); us += ldsf(sb + SM_GRED + q * 256 + 128 + lane * 4); }
                    gs = rbf(gs); us = rbf(us);
                    st_rlx(p.scr + G_H + (pair * 32 + lane) * 4, f2bf(rbf(gs * fsigm(gs)) * us) << 16 | tagbit);
                }
            }
            STAMPT(15, 384);
            if (w == 15) {
            if (lane == 0) {
                const unsigned target = (ep + 1) * NCTA; int n = 0; unsigned v;
                do { asm volatile("ld.acquire.gpu.global.u32 %0, [%1];" : "=r"(v) : "l"(p.scr + G_CNT2) : "memory"); } while ((int)(v - target) < 0 && ++n < SPIN_MAX);
                fence_async_g();
            }
            __syncwarp();
            const int rho = lane & 7;
#pragma unroll 1
            for (int G = 0; G < 4; G++) {
                const int t0 = 128 * (4 * G + 2 * rank);
                mbar_wait(sb + MB_TILE + 8 * G);
                if (G == 3) STAMPT(19, 480);
                if (G == 2) STAMPT(20, 480);
                uint32_t r[8][4];
#pragma unroll
                for (int it = 0; it < 8; it++) {
                    const int kb = 4 * (it & 3) + (lane >> 3);
                    ldsm4t(r[it], sb + SM_S + G * 4096 + (it >> 2) * 2048 + rho * 256 + (((kb & 8) | ((kb & 7) ^ rho)) << 4));
                }
                __syncwarp();
#pragma unroll
                for (int it = 0; it < 8; it++) stsm4(sb + SM_S + G * 4096 + (32 * it + lane) * 16, r[it][0], r[it][1], r[it][2], r[it][3]);
                const int rel = idx - t0;
                if (rel >= 0 && rel < 256) {
                    __syncwarp();
                    if (lane < 4) {
                        const uint32_t ra = sb + SM_S + G * 4096 + rel * 16 + lane * 4;
                        sts32(sb + M_VS + lane * 4, lds32(ra)); sts32(ra, 0); mbar_arrive(sb + MB_VS);
                    }
                }
                fence_async();
                __syncwarp();
                if (lane == 0) {
                    asm volatile("cp.reduce.async.bulk.tensor.2d.global.shared::cta.add.tile.bulk_group [%0, {%2, %3}], [%1];"
                        :: "l"((uint64_t)&tm_out), "r"(sb + SM_S + G * 4096), "r"(pair * 8), "r"(t0) : "memory");
                    asm volatile("cp.async.bulk.commit_group;" ::: "memory");
                }
            }
            STAMPT(21, 480);
            if (lane == 0) asm volatile("cp.async.bulk.wait_group 0;" ::: "memory");
            STAMPT(11, 480);
        } else {
            {
                float acc[2][4];
#pragma unroll
                for (int i = 0; i < 2; i++) acc[i][0] = acc[i][1] = acc[i][2] = acc[i][3] = 0.f;
                {
                    const uint32_t* hp = (const uint32_t*)(p.scr + G_H) + (b & 7) * 224;
                    uint2 h0, h1 = make_uint2(tagbit, tagbit); int n = 0;
                    do { h0 = ld_rlx2(hp + 2 * t3); if (t3 < 16) h1 = ld_rlx2(hp + 192 + 2 * t3); }
                    while (__any_sync(~0u, ((h0.x ^ tagbit) | (h0.y ^ tagbit) | (h1.x ^ tagbit) | (h1.y ^ tagbit)) & 1) && ++n < SPIN_MAX);
                    bar_sync(7, 96);
                    sts32(sb + M_XS + t3 * 4, __byte_perm(h0.x, h0.y, 0x7632));
                    if (t3 < 16) sts32(sb + M_XS + 384 + t3 * 4, __byte_perm(h1.x, h1.y, 0x7632));
                    bar_sync(7, 96);
                }
                STAMPT(47, 384);
                mbar_wait(sb + MB_W2);
#pragma unroll
                for (int k = 0; k < 5; k++) {
                    const int s = min(mw + 3 * k, 13);
                    const bool on = mw + 3 * k < 14 && g == 0;
                    const uint32_t xa = sb + M_XS + (s * 16 + 2 * c) * 2;
                    const uint32_t v0 = lds32(xa), v1 = lds32(xa + 16), b0 = on ? v0 : 0u, b1 = on ? v1 : 0u;
                    const int row = s * 16 + (lane & 7) + (lane >> 4) * 8;
#pragma unroll
                    for (int mt = 0; mt < 2; mt++) {
                        uint32_t f[4];
                        const int chunk = mt * 2 + ((lane >> 3) & 1);
                        ldsm4t(f, sb + SM_WD + row * 64 + ((chunk ^ ((row >> 1) & 3)) << 4));
                        mma_b(acc[mt], f[0], f[1], f[2], f[3], b0, b1);
                    }
                }
                if (c == 0) {
#pragma unroll
                    for (int i = 0; i < 2; i++) { stsf(sb + M_RED + mw * 128 + i * 64 + g * 4, acc[i][0]); stsf(sb + M_RED + mw * 128 + i * 64 + 32 + g * 4, acc[i][2]); }
                }
                bar_sync(7, 96);
                if (mw == 0) {
                    const float s = ldsf(sb + M_RED + lane * 4) + ldsf(sb + M_RED + 128 + lane * 4) + ldsf(sb + M_RED + 256 + lane * 4);
                    st_rlx(p.scr + G_PART + (b * 32 + lane) * 4, (__float_as_uint(s) & ~1u) | tagbit);
                }
            }
            STAMPT(16, 384);
            if (mw == 0 && rank == ((idx >> 8) & 1)) {
                const uint32_t* pp = (const uint32_t*)(p.scr + G_PART) + ((pair >> 2) * 8 + g) * 32 + (pair & 3) * 8 + 2 * c;
                uint2 v; int n = 0;
                do { v = ld_rlx2(pp); } while (__any_sync(~0u, ((v.x ^ tagbit) | (v.y ^ tagbit)) & 1) && ++n < SPIN_MAX);
                float s0 = __uint_as_float(v.x & ~1u), s1 = __uint_as_float(v.y & ~1u);
#pragma unroll
                for (int o = 4; o < 32; o <<= 1) { s0 += __shfl_xor_sync(~0u, s0, o); s1 += __shfl_xor_sync(~0u, s1, o); }
                mbar_wait(sb + MB_VS);
                if (g == 0) {
                    const uint32_t sk = k0 >> 16, rb = (sk & 0x8000) ? (sk & 0x7FFF) : (~sk & 0xFFFF);
                    const float rsel = rbf(fsigm(bf2f(rb)));
                    const uint32_t vv = lds32(sb + M_VS + c * 4);
                    const uint32_t o = pk_b(bf2f(vv & 0xFFFF) + rbf(rbf(s0) * rsel), bf2f(vv >> 16) + rbf(rbf(s1) * rsel));
                    asm volatile("red.relaxed.gpu.global.add.noftz.bf16x2 [%0], %1;" :: "l"(p.out + (size_t)idx * 512 + pair * 8 + 2 * c), "r"(o) : "memory");
                }
            }
            STAMPT(17, 384);
        }
    }
    if (b == 0 && tid == 0) *(volatile unsigned*)(p.scr + G_EPOCH) = ep + 1;
    STAMPT(18, 0);
}

typedef CUresult (*EncFn)(CUtensorMap*, CUtensorMapDataType, cuuint32_t, void*, const cuuint64_t*, const cuuint64_t*, const cuuint32_t*, const cuuint32_t*,
                          CUtensorMapInterleave, CUtensorMapSwizzle, CUtensorMapL2promotion, CUtensorMapFloatOOBfill);

static CUtensorMap make_map2(EncFn enc, void* ptr, int cols, int rows, int bx, int by, CUtensorMapSwizzle sw) {
    CUtensorMap m;
    cuuint64_t dim[2] = {(cuuint64_t)cols, (cuuint64_t)rows}, str[1] = {(cuuint64_t)cols * 2};
    cuuint32_t box[2] = {(cuuint32_t)bx, (cuuint32_t)by}, es[2] = {1, 1};
    enc(&m, CU_TENSOR_MAP_DATA_TYPE_BFLOAT16, 2, ptr, dim, str, box, es, CU_TENSOR_MAP_INTERLEAVE_NONE, sw, CU_TENSOR_MAP_L2_PROMOTION_NONE, CU_TENSOR_MAP_FLOAT_OOB_FILL_NONE);
    return m;
}

extern "C" void kernel_launch(void* const* d_in, const int* in_sizes, int n_in, void* d_out, int out_size) {
    static bool init = false;
    static CUtensorMap tm_s1, tm_out, tm_wg, tm_wu, tm_wd;
    static void* cached_out = nullptr;
    static void* scr = nullptr;
    if (!init || cached_out != d_out) {
        cudaFuncSetAttribute(fused_kernel, cudaFuncAttributeMaxDynamicSharedMemorySize, SMEM_BYTES);
        void* fn = nullptr; cudaDriverEntryPointQueryResult q;
        cudaGetDriverEntryPoint("cuTensorMapEncodeTiled", &fn, cudaEnableDefault, &q);
        EncFn enc = (EncFn)fn;
        cudaGetSymbolAddress(&scr, g_scr);
        void* s1 = (uint8_t*)scr + G_S1;
        {
            cuuint64_t dim[3] = {4096, 128, 2}, str[2] = {16384, 8192};
            cuuint32_t box[3] = {32, 128, 2}, es[3] = {1, 1, 1};
            enc(&tm_s1, CU_TENSOR_MAP_DATA_TYPE_BFLOAT16, 3, s1, dim, str, box, es, CU_TENSOR_MAP_INTERLEAVE_NONE, CU_TENSOR_MAP_SWIZZLE_NONE,
                CU_TENSOR_MAP_L2_PROMOTION_NONE, CU_TENSOR_MAP_FLOAT_OOB_FILL_NONE);
        }
        tm_out = make_map2(enc, d_out, 512, 2048, 8, 256, CU_TENSOR_MAP_SWIZZLE_NONE);
        tm_wg = make_map2(enc, d_in[11], 1792, 512, 32, 256, CU_TENSOR_MAP_SWIZZLE_64B);
        tm_wu = make_map2(enc, d_in[12], 1792, 512, 32, 256, CU_TENSOR_MAP_SWIZZLE_64B);
        tm_wd = make_map2(enc, d_in[13], 512, 1792, 32, 224, CU_TENSOR_MAP_SWIZZLE_64B);
        cached_out = d_out; init = true;
    }
    Params p;
    p.x = (const uint16_t*)d_in[0]; p.Are = (const uint16_t*)d_in[1]; p.Aim = (const uint16_t*)d_in[2];
    p.Bre = (const uint16_t*)d_in[3]; p.Bim = (const uint16_t*)d_in[4]; p.Cre = (const uint16_t*)d_in[5]; p.Cim = (const uint16_t*)d_in[6];
    p.ldt = (const uint16_t*)d_in[7]; p.Dsk = (const uint16_t*)d_in[8]; p.wr = (const uint16_t*)d_in[10]; p.out = (uint16_t*)d_out;
    p.scr = (uint8_t*)scr; p.wg = (const uint8_t*)d_in[11]; p.wu = (const uint8_t*)d_in[12]; p.wd = (const uint8_t*)d_in[13];
    fused_kernel<<<NCTA, NTHR, SMEM_BYTES, cudaStreamPerThread>>>(p, tm_s1, tm_out, tm_wg, tm_wu, tm_wd);
}
```
